```python
import torch

def _softmax(x, axis=-1):
    return torch.softmax(x, dim=axis)
def _gelu(x):
    return torch.nn.functional.gelu(x, approximate="tanh")
def _silu(x):
    return torch.nn.functional.silu(x)
def _sigmoid(x):
    return torch.sigmoid(x)
def _layernorm(x, axis=-1, eps=1e-5):
    m = x.mean(dim=axis, keepdim=True)
    v = x.var(dim=axis, keepdim=True, unbiased=False)
    return (x - m) / torch.sqrt(v + eps)
def _scatter_add(tgt, idx, src, axis=0):
    return tgt.clone().index_add_(axis, idx, src)
def _segment_sum(src, seg, n):
    out = torch.zeros((n,) + src.shape[1:], dtype=src.dtype)
    return out.index_add_(0, seg, src)
def _pad(x, pw):
    flat = tuple(v for pair in reversed(pw) for v in pair)
    return torch.nn.functional.pad(x, flat)

kernel_name = 'standalone__attention_interact_autoint__recsys'

def setup_inputs():

    _w = (lambda a: (lambda t: t.to(torch.bfloat16) if t.is_floating_point() else t)(torch.as_tensor(a)))
    B, F = 4096, 100
    D = max(2, (16 // 2) * 2)
    H = 2
    Dh = D // H
    return {
        "e": _w((lambda *s: torch.randn(*s, dtype=torch.bfloat16) * 0.05)(B, F, D).to(float)),
        "wq": _w((lambda *s: torch.randn(*s, dtype=torch.bfloat16) * 6.4)(H, D, Dh).to(float)),
        "wk": _w((lambda *s: torch.randn(*s, dtype=torch.bfloat16) * 6.4)(H, D, Dh).to(float)),
        "wv": _w((lambda *s: torch.randn(*s, dtype=torch.bfloat16) * 0.05)(H, D, Dh).to(float)),
        "wres": _w((lambda *s: torch.randn(*s, dtype=torch.bfloat16) * 0.05)(D, D).to(float)),
    }

def reference(e, wq, wk, wv, wres):
    H, D, Dh = wq.shape[0], wq.shape[1], wq.shape[2]
    B, F = e.shape[0], e.shape[1]
    q = torch.einsum('bfd,hdk->bhfk', e, wq)
    k = torch.einsum('bfd,hdk->bhfk', e, wk)
    v = torch.einsum('bfd,hdk->bhfk', e, wv)
    scale = float(Dh) ** -0.5
    scores = torch.einsum('bhfk,bhgk->bhfg', q, k) * scale
    attn = _softmax(scores, axis=-1)
    attn = (lambda x, dt: x.to(dt))(attn, v.dtype)
    ctx = torch.einsum('bhfg,bhgk->bhfk', attn, v)
    ctx = (lambda x, *d: x.permute(*d))(ctx, 0, 2, 1, 3).reshape(B, F, H * Dh)
    res = torch.einsum('bfd,de->bfe', e, wres)
    out = ctx + res
    mask = (lambda x, dt: x.to(dt))(out > 0, out.dtype)
    return out * mask
```

```cpp
#include <cuda_runtime.h>
#include <cuda_bf16.h>
#include <stdint.h>

namespace {

#define MUW 0xA
#define BTOK 2
#define PFDELAY 1000
constexpr int NF = 100;
constexpr int NWG = 4;
constexpr int BPW = 8;
constexpr int NCTA = 132, NHEAVY = 4;
constexpr int E_BYTES = NF * 32;

constexpr int L = 14 * 128;
constexpr int KV_ONE = 0, KV_V0 = L, KV_V1 = 2 * L, KV_K0 = 3 * L, KV_E = 5 * L, KV_SZ = KV_E + E_BYTES;
constexpr int WG_KI = 0, WG_KV = 2 * L, WG_SZ = WG_KV + 4 * KV_SZ;
constexpr int SM_W = NWG * WG_SZ;
constexpr int SM_DUMMY = SM_W + 10 * 256;
constexpr int SM_BAR = SM_DUMMY + 16;
constexpr int SM_TOTAL = SM_BAR + 8 * BPW * NWG;

__host__ __device__ constexpr bool mufu_tile(int n) { return n >= 12 || (n % 3 == 2 && ((MUW >> (n / 3)) & 1)); }
constexpr uint32_t mu_mask() { uint32_t m = 0; for (int n = 0; n < 14; n++) m |= (mufu_tile(n) ? 1u : 0u) << n; return m; }
constexpr uint32_t MU_MASK = mu_mask();
struct Wp { const __nv_bfloat16* p[4]; };

__device__ __forceinline__ void wg_proj64(uint32_t* d, uint32_t a0, uint32_t a1, uint32_t a2, uint32_t a3, uint64_t db) {
    asm volatile("wgmma.mma_async.sync.aligned.m64n64k16.f32.bf16.bf16 {"
        "%0, %1, %2, %3, %4, %5, %6, %7, %8, %9, %10, %11, %12, %13, %14, %15, %16, %17, %18, %19, %20, %21, %22, %23, "
        "%24, %25, %26, %27, %28, %29, %30, %31"
        "}, {%32, %33, %34, %35}, %36, 0, 1, 1, 1;"
        : "=r"(d[0]), "=r"(d[1]), "=r"(d[2]), "=r"(d[3]), "=r"(d[4]), "=r"(d[5]), "=r"(d[6]), "=r"(d[7]), "=r"(d[8]),
          "=r"(d[9]), "=r"(d[10]), "=r"(d[11]), "=r"(d[12]), "=r"(d[13]), "=r"(d[14]), "=r"(d[15]), "=r"(d[16]),
          "=r"(d[17]), "=r"(d[18]), "=r"(d[19]), "=r"(d[20]), "=r"(d[21]), "=r"(d[22]), "=r"(d[23]), "=r"(d[24]),
          "=r"(d[25]), "=r"(d[26]), "=r"(d[27]), "=r"(d[28]), "=r"(d[29]), "=r"(d[30]), "=r"(d[31])
        : "r"(a0), "r"(a1), "r"(a2), "r"(a3), "l"(db));
}

__device__ __forceinline__ void wg_s104(uint32_t* d, uint32_t a0, uint32_t a1, uint32_t a2, uint32_t a3, uint64_t db) {
    asm volatile("wgmma.mma_async.sync.aligned.m64n104k16.f32.bf16.bf16 {"
        "%0, %1, %2, %3, %4, %5, %6, %7, %8, %9, %10, %11, %12, %13, %14, %15, %16, %17, %18, %19, %20, %21, %22, %23, "
        "%24, %25, %26, %27, %28, %29, %30, %31, %32, %33, %34, %35, %36, %37, %38, %39, %40, %41, %42, %43, %44, %45, "
        "%46, %47, %48, %49, %50, %51"
        "}, {%52, %53, %54, %55}, %56, 0, 1, 1, 0;"
        : "=r"(d[0]), "=r"(d[1]), "=r"(d[2]), "=r"(d[3]), "=r"(d[4]), "=r"(d[5]), "=r"(d[6]), "=r"(d[7]), "=r"(d[8]),
          "=r"(d[9]), "=r"(d[10]), "=r"(d[11]), "=r"(d[12]), "=r"(d[13]), "=r"(d[14]), "=r"(d[15]), "=r"(d[16]),
          "=r"(d[17]), "=r"(d[18]), "=r"(d[19]), "=r"(d[20]), "=r"(d[21]), "=r"(d[22]), "=r"(d[23]), "=r"(d[24]),
          "=r"(d[25]), "=r"(d[26]), "=r"(d[27]), "=r"(d[28]), "=r"(d[29]), "=r"(d[30]), "=r"(d[31]), "=r"(d[32]),
          "=r"(d[33]), "=r"(d[34]), "=r"(d[35]), "=r"(d[36]), "=r"(d[37]), "=r"(d[38]), "=r"(d[39]), "=r"(d[40]),
          "=r"(d[41]), "=r"(d[42]), "=r"(d[43]), "=r"(d[44]), "=r"(d[45]), "=r"(d[46]), "=r"(d[47]), "=r"(d[48]),
          "=r"(d[49]), "=r"(d[50]), "=r"(d[51])
        : "r"(a0), "r"(a1), "r"(a2), "r"(a3), "l"(db));
}

__device__ __forceinline__ void wg_s104sp(uint32_t* d, uint32_t a0, uint32_t a1, uint32_t a2, uint32_t a3, uint64_t db, uint32_t meta) {
    asm volatile("wgmma.mma_async.sp.sync.aligned.m64n104k32.f32.bf16.bf16 {"
        "%0, %1, %2, %3, %4, %5, %6, %7, %8, %9, %10, %11, %12, %13, %14, %15, %16, %17, %18, %19, %20, %21, %22, %23, "
        "%24, %25, %26, %27, %28, %29, %30, %31, %32, %33, %34, %35, %36, %37, %38, %39, %40, %41, %42, %43, %44, %45, "
        "%46, %47, %48, %49, %50, %51"
        "}, {%52, %53, %54, %55}, %56, %57, 0, 0, 1, 1, 0;"
        : "=r"(d[0]), "=r"(d[1]), "=r"(d[2]), "=r"(d[3]), "=r"(d[4]), "=r"(d[5]), "=r"(d[6]), "=r"(d[7]), "=r"(d[8]),
          "=r"(d[9]), "=r"(d[10]), "=r"(d[11]), "=r"(d[12]), "=r"(d[13]), "=r"(d[14]), "=r"(d[15]), "=r"(d[16]),
          "=r"(d[17]), "=r"(d[18]), "=r"(d[19]), "=r"(d[20]), "=r"(d[21]), "=r"(d[22]), "=r"(d[23]), "=r"(d[24]),
          "=r"(d[25]), "=r"(d[26]), "=r"(d[27]), "=r"(d[28]), "=r"(d[29]), "=r"(d[30]), "=r"(d[31]), "=r"(d[32]),
          "=r"(d[33]), "=r"(d[34]), "=r"(d[35]), "=r"(d[36]), "=r"(d[37]), "=r"(d[38]), "=r"(d[39]), "=r"(d[40]),
          "=r"(d[41]), "=r"(d[42]), "=r"(d[43]), "=r"(d[44]), "=r"(d[45]), "=r"(d[46]), "=r"(d[47]), "=r"(d[48]),
          "=r"(d[49]), "=r"(d[50]), "=r"(d[51])
        : "r"(a0), "r"(a1), "r"(a2), "r"(a3), "l"(db), "r"(meta));
}

__device__ __forceinline__ void wg_pv16_0(uint32_t* d, uint32_t a0, uint32_t a1, uint32_t a2, uint32_t a3, uint64_t db) {
    asm volatile("wgmma.mma_async.sync.aligned.m64n16k16.f32.bf16.bf16 {"
        "%0, %1, %2, %3, %4, %5, %6, %7"
        "}, {%8, %9, %10, %11}, %12, 0, 1, 1, 1;"
        : "=r"(d[0]), "=r"(d[1]), "=r"(d[2]), "=r"(d[3]), "=r"(d[4]), "=r"(d[5]), "=r"(d[6]), "=r"(d[7])
        : "r"(a0), "r"(a1), "r"(a2), "r"(a3), "l"(db));
}

__device__ __forceinline__ void wg_pv16(uint32_t* d, uint32_t a0, uint32_t a1, uint32_t a2, uint32_t a3, uint64_t db) {
    asm volatile("wgmma.mma_async.sync.aligned.m64n16k16.f32.bf16.bf16 {"
        "%0, %1, %2, %3, %4, %5, %6, %7"
        "}, {%8, %9, %10, %11}, %12, 1, 1, 1, 1;"
        : "+r"(d[0]), "+r"(d[1]), "+r"(d[2]), "+r"(d[3]), "+r"(d[4]), "+r"(d[5]), "+r"(d[6]), "+r"(d[7])
        : "r"(a0), "r"(a1), "r"(a2), "r"(a3), "l"(db));
}

__device__ __forceinline__ void wg_pv24_0(uint32_t* d, uint32_t a0, uint32_t a1, uint32_t a2, uint32_t a3, uint64_t db) {
    asm volatile("wgmma.mma_async.sync.aligned.m64n24k16.f32.bf16.bf16 {"
        "%0, %1, %2, %3, %4, %5, %6, %7, %8, %9, %10, %11"
        "}, {%12, %13, %14, %15}, %16, 0, 1, 1, 1;"
        : "=r"(d[0]), "=r"(d[1]), "=r"(d[2]), "=r"(d[3]), "=r"(d[4]), "=r"(d[5]), "=r"(d[6]), "=r"(d[7]), "=r"(d[8]),
          "=r"(d[9]), "=r"(d[10]), "=r"(d[11])
        : "r"(a0), "r"(a1), "r"(a2), "r"(a3), "l"(db));
}

__device__ __forceinline__ void wg_pv24(uint32_t* d, uint32_t a0, uint32_t a1, uint32_t a2, uint32_t a3, uint64_t db) {
    asm volatile("wgmma.mma_async.sync.aligned.m64n24k16.f32.bf16.bf16 {"
        "%0, %1, %2, %3, %4, %5, %6, %7, %8, %9, %10, %11"
        "}, {%12, %13, %14, %15}, %16, 1, 1, 1, 1;"
        : "+r"(d[0]), "+r"(d[1]), "+r"(d[2]), "+r"(d[3]), "+r"(d[4]), "+r"(d[5]), "+r"(d[6]), "+r"(d[7]), "+r"(d[8]),
          "+r"(d[9]), "+r"(d[10]), "+r"(d[11])
        : "r"(a0), "r"(a1), "r"(a2), "r"(a3), "l"(db));
}

#define WG_FENCE() asm volatile("wgmma.fence.sync.aligned;" ::: "memory")
#define WG_COMMIT() asm volatile("wgmma.commit_group.sync.aligned;" ::: "memory")
#define WG_WAIT0() asm volatile("wgmma.wait_group.sync.aligned 0;" ::: "memory")
template <int N> __device__ __forceinline__ void pin(uint32_t* r) {
#pragma unroll
    for (int i = 0; i < N; i++) asm volatile("" : "+r"(r[i])::"memory");
}
__device__ __forceinline__ uint64_t mkdesc(uint32_t addr, uint32_t lbo, uint32_t sbo) {
    return (uint64_t)((addr >> 4) | ((lbo >> 4) << 16)) | ((uint64_t)(sbo >> 4) << 32);
}
__device__ __forceinline__ uint32_t packbf(uint32_t lo, uint32_t hi) {
    uint32_t r; asm("cvt.rn.bf16x2.f32 %0, %1, %2;" : "=r"(r) : "r"(hi), "r"(lo)); return r;
}
__device__ __forceinline__ uint32_t packbf_relu(float lo, float hi) {
    uint32_t r; asm("cvt.rn.relu.bf16x2.f32 %0, %1, %2;" : "=r"(r) : "f"(hi), "f"(lo)); return r;
}
__device__ __forceinline__ uint32_t exp_mufu(uint32_t x0, uint32_t x1) {
    uint32_t y0, y1;
    asm("ex2.approx.ftz.f32 %0, %1;" : "=r"(y0) : "r"(x0));
    asm("ex2.approx.ftz.f32 %0, %1;" : "=r"(y1) : "r"(x1));
    return packbf(y0, y1);
}
__device__ __forceinline__ uint32_t exp_fma(uint32_t x0, uint32_t x1, uint32_t kc, uint32_t m1) {
    uint32_t I, m, E, r;
    asm("cvt.pack.sat.s16.s32 %0, %1, %2;" : "=r"(I) : "r"(x1), "r"(x0));
    asm("lop3.b32 %0, %1, 0x007F007F, %2, 0xEA;" : "=r"(m) : "r"(I), "r"(kc));
    asm("mad.lo.s32 %0, %1, %2, %3;" : "=r"(E) : "r"(m), "r"(m1), "r"(I));
    asm("fma.rn.relu.bf16x2 %0, %1, %2, %3;" : "=r"(r) : "r"(I), "r"(m), "r"(E));
    return r;
}
__device__ __forceinline__ uint32_t mulbf(uint32_t a, uint32_t b) {
    uint32_t r; asm("mul.rn.bf16x2 %0, %1, %2;" : "=r"(r) : "r"(a), "r"(b)); return r;
}
__device__ __forceinline__ void sts64(uint32_t a, uint32_t x, uint32_t y) {
    asm volatile("st.shared.v2.b32 [%0], {%1, %2};" :: "r"(a), "r"(x), "r"(y) : "memory");
}
__device__ __forceinline__ void bar_sync(int id, int n) { asm volatile("bar.sync %0, %1;" :: "r"(id), "r"(n) : "memory"); }
__device__ __forceinline__ void bar_arrive(int id, int n) { asm volatile("bar.arrive %0, %1;" :: "r"(id), "r"(n) : "memory"); }
__device__ __forceinline__ float rcp(uint32_t x) {
    float r; asm("rcp.approx.ftz.f32 %0, %1;" : "=f"(r) : "r"(x)); return r;
}
__device__ __forceinline__ void ldsm4(uint32_t* r, uint32_t a) {
    asm volatile("ldmatrix.sync.aligned.m8n8.x4.shared.b16 {%0,%1,%2,%3}, [%4];"
                 : "=r"(r[0]), "=r"(r[1]), "=r"(r[2]), "=r"(r[3]) : "r"(a) : "memory");
}
__device__ __forceinline__ void ldsm4t(uint32_t* r, uint32_t a) {
    asm volatile("ldmatrix.sync.aligned.m8n8.x4.trans.shared.b16 {%0,%1,%2,%3}, [%4];"
                 : "=r"(r[0]), "=r"(r[1]), "=r"(r[2]), "=r"(r[3]) : "r"(a) : "memory");
}
__device__ __forceinline__ void ldsm2(uint32_t* r, uint32_t a) {
    asm volatile("ldmatrix.sync.aligned.m8n8.x2.shared.b16 {%0,%1}, [%2];" : "=r"(r[0]), "=r"(r[1]) : "r"(a) : "memory");
}
__device__ __forceinline__ void ldsm2t(uint32_t* r, uint32_t a) {
    asm volatile("ldmatrix.sync.aligned.m8n8.x2.trans.shared.b16 {%0,%1}, [%2];" : "=r"(r[0]), "=r"(r[1]) : "r"(a) : "memory");
}
__device__ __forceinline__ void hmma8(uint32_t* d, uint32_t a0, uint32_t a1, uint32_t b0) {
    asm("mma.sync.aligned.m16n8k8.row.col.f32.bf16.bf16.f32 {%0,%1,%2,%3}, {%4,%5}, {%6}, {%0,%1,%2,%3};"
        : "+r"(d[0]), "+r"(d[1]), "+r"(d[2]), "+r"(d[3]) : "r"(a0), "r"(a1), "r"(b0));
}
__device__ __forceinline__ void stsm4(uint32_t a, uint32_t r0, uint32_t r1, uint32_t r2, uint32_t r3) {
    asm volatile("stmatrix.sync.aligned.m8n8.x4.shared.b16 [%0], {%1,%2,%3,%4};"
                 :: "r"(a), "r"(r0), "r"(r1), "r"(r2), "r"(r3) : "memory");
}
__device__ __forceinline__ void hmma(uint32_t* d, uint32_t a0, uint32_t a1, uint32_t a2, uint32_t a3, uint32_t b0, uint32_t b1) {
    asm("mma.sync.aligned.m16n8k16.row.col.f32.bf16.bf16.f32 {%0,%1,%2,%3}, {%4,%5,%6,%7}, {%8,%9}, {%0,%1,%2,%3};"
        : "+r"(d[0]), "+r"(d[1]), "+r"(d[2]), "+r"(d[3]) : "r"(a0), "r"(a1), "r"(a2), "r"(a3), "r"(b0), "r"(b1));
}
__device__ __forceinline__ void hmma0(uint32_t* d, uint32_t a0, uint32_t a1, uint32_t a2, uint32_t a3, uint32_t b0, uint32_t b1) {
    asm("mma.sync.aligned.m16n8k16.row.col.f32.bf16.bf16.f32 {%0,%1,%2,%3}, {%4,%5,%6,%7}, {%8,%9}, {%10,%10,%10,%10};"
        : "=r"(d[0]), "=r"(d[1]), "=r"(d[2]), "=r"(d[3]) : "r"(a0), "r"(a1), "r"(a2), "r"(a3), "r"(b0), "r"(b1), "r"(0));
}
__device__ __forceinline__ void load_e(uint32_t dst, const void* src, uint32_t bar) {
    asm volatile("mbarrier.arrive.expect_tx.shared::cta.b64 _, [%0], %1;" :: "r"(bar), "n"(E_BYTES) : "memory");
    asm volatile("cp.async.bulk.shared::cluster.global.mbarrier::complete_tx::bytes [%0], [%1], %2, [%3];"
                 :: "r"(dst), "l"(src), "n"(E_BYTES), "r"(bar) : "memory");
}
__device__ __forceinline__ void wait_bar(uint32_t bar) {
    asm volatile("{\n.reg .pred p;\n.reg .u32 n;\n"
                 "mbarrier.try_wait.parity.shared::cta.b64 p, [%0], 0;\n"
                 "@p bra DONE;\n"
                 "mov.u32 n, %%nwarpid;\n"
                 "SPIN:\n"
                 "mbarrier.try_wait.parity.shared::cta.b64 p, [%0], 0;\n"
                 "add.u32 n, n, 32;\n"
                 "setp.gt.or.u32 p, n, 0x7FFFFFF, p;\n"
                 "@!p bra SPIN;\n"
                 "DONE:\n}" :: "r"(bar) : "memory");
}
__device__ __forceinline__ uint32_t opaque(uint32_t x) { asm volatile("" : "+r"(x)); return x; }
__device__ __forceinline__ uint32_t umax3(uint32_t a, uint32_t b, uint32_t c) { return __vimax3_u32(a, b, c); }
__device__ __forceinline__ float bf2f(__nv_bfloat16 x) { return __bfloat162float(x); }
__device__ __forceinline__ float rbf(float x) { return __bfloat162float(__float2bfloat16_rn(x)); }

__device__ __noinline__ void slow_batch(const __nv_bfloat16* __restrict__ e, const __nv_bfloat16* __restrict__ wq,
                                        const __nv_bfloat16* __restrict__ wk, const __nv_bfloat16* __restrict__ wv,
                                        const __nv_bfloat16* __restrict__ wres, __nv_bfloat16* __restrict__ out,
                                        float* sk, float* sv) {
    const int tid = threadIdx.x;
    for (int i = tid; i < NF * 16; i += NWG * 128) {
        int r = i >> 4, c = i & 15, h = c >> 3, k = c & 7;
        float ak = 0.f, av = 0.f;
        for (int d = 0; d < 16; d++) {
            float x = bf2f(e[r * 16 + d]);
            ak += x * bf2f(wk[h * 128 + d * 8 + k]);
            av += x * bf2f(wv[h * 128 + d * 8 + k]);
        }
        sk[i] = rbf(ak); sv[i] = rbf(av);
    }
    __syncthreads();
    for (int i = tid; i < 2 * NF; i += NWG * 128) {
        int r = i >> 1, h = i & 1;
        float q[8], res[8], o[8];
#pragma unroll
        for (int k = 0; k < 8; k++) {
            float aq = 0.f, ar = 0.f;
            for (int d = 0; d < 16; d++) {
                float x = bf2f(e[r * 16 + d]);
                aq += x * bf2f(wq[h * 128 + d * 8 + k]);
                ar += x * bf2f(wres[d * 16 + h * 8 + k]);
            }
            q[k] = rbf(aq); res[k] = rbf(ar); o[k] = 0.f;
        }
        float mx = -INFINITY, l = 0.f;
        for (int pass = 0; pass < 3; pass++) {
            for (int j = 0; j < NF; j++) {
                float s = 0.f;
#pragma unroll
                for (int k = 0; k < 8; k++) s += q[k] * sk[j * 16 + h * 8 + k];
                s = rbf(rbf(s) * 0.35355339059327373f);
                if (pass == 0) mx = fmaxf(mx, s);
                else if (pass == 1) l += expf(s - mx);
                else {
                    float p = rbf(expf(s - mx) / l);
#pragma unroll
                    for (int k = 0; k < 8; k++) o[k] += p * sv[j * 16 + h * 8 + k];
                }
            }
        }
#pragma unroll
        for (int k = 0; k < 8; k++) {
            float y = rbf(rbf(o[k]) + res[k]);
            out[r * 16 + h * 8 + k] = __float2bfloat16_rn(y > 0.f ? y : y * 0.f);
        }
    }
    __syncthreads();
}

template <int NREG, bool WIDE>
__device__ __forceinline__ void pv_chain(uint32_t* o, const uint32_t* p, uint64_t dv, uint32_t z0, uint32_t z1) {
    if (WIDE) wg_pv24_0(o, p[0], p[1], p[2], p[3], dv); else wg_pv16_0(o, p[0], p[1], p[2], p[3], dv);
#pragma unroll
    for (int s = 1; s < 6; s++) {
        if (WIDE) wg_pv24(o, p[4 * s], p[4 * s + 1], p[4 * s + 2], p[4 * s + 3], dv + 16 * s);
        else wg_pv16(o, p[4 * s], p[4 * s + 1], p[4 * s + 2], p[4 * s + 3], dv + 16 * s);
    }
    if (WIDE) wg_pv24(o, p[24], p[25], z0, z1, dv + 96); else wg_pv16(o, p[24], p[25], z0, z1, dv + 96);
}

__device__ __forceinline__ void exp_tile(uint32_t* p, const uint32_t* s, uint32_t kc, uint32_t m1) {
    p[24] = exp_mufu(s[48], s[49]); p[25] = exp_mufu(s[50], s[51]);
#pragma unroll
    for (int i = 0; i < 24; i++) p[i] = mufu_tile(i >> 1) ? exp_mufu(s[2 * i], s[2 * i + 1]) : exp_fma(s[2 * i], s[2 * i + 1], kc, m1);
}
constexpr uint32_t CHK_OFF = 0xE080E080u;
constexpr uint32_t CHK_LIM = 0x4000u;
__device__ __forceinline__ void finish(uint32_t* pa, uint32_t* pb, uint32_t la, uint32_t lb, uint32_t a0, uint32_t a1,
                                       uint32_t b0, uint32_t b1, uint32_t resa, uint32_t resb, uint32_t& chk) {
    const uint32_t ra = __float_as_uint(rcp(la)), rb = __float_as_uint(rcp(lb));
    const uint32_t rr = packbf(ra, rb);
    chk = __viaddmax_u16x2(rr, CHK_OFF, chk);
    const uint32_t oa = packbf(a0, a1), ob = packbf(b0, b1);
    uint32_t ya, yb;
    asm("{.reg .b16 l, h; .reg .b32 t; mov.b32 {l, h}, %2; mov.b32 t, {l, l}; fma.rn.relu.bf16x2 %0, %1, t, %3;}" : "=r"(ya) : "r"(oa), "r"(rr), "r"(resa));
    asm("{.reg .b16 l, h; .reg .b32 t; mov.b32 {l, h}, %2; mov.b32 t, {h, h}; fma.rn.relu.bf16x2 %0, %1, t, %3;}" : "=r"(yb) : "r"(ob), "r"(rr), "r"(resb));
    *pa = ya; *pb = yb;
}
#define TOK_PUT(n) do { if (BTOK == n) bar_arrive(tok_nx, 256); } while (0)
__device__ __forceinline__ uint64_t mk64(uint32_t lo, uint32_t hi) {
    uint64_t r; asm("mov.b64 %0, {%1, %2};" : "=l"(r) : "r"(lo), "r"(hi)); return r;
}
__device__ __forceinline__ uint32_t ldg32(const uint32_t* p) {
    uint32_t r; asm volatile("ld.global.nc.b32 %0, [%1];" : "=r"(r) : "l"(p) : "memory"); return r;
}
__device__ __forceinline__ uint32_t uni(uint32_t x) { return __shfl_sync(0xffffffffu, x, 0); }

__global__ void __launch_bounds__(NWG * 128, 1)
autoint_kernel(const __nv_bfloat16* __restrict__ e, const __grid_constant__ Wp wp, __nv_bfloat16* __restrict__ out, uint32_t m1) {
    extern __shared__ __align__(128) uint8_t smem[];
    const uint32_t sb = (uint32_t)__cvta_generic_to_shared(smem);
    const int tid = threadIdx.x, lane = tid & 31, tw = tid & 127;
    const int g = lane >> 2, t = lane & 3;
    const int cb = blockIdx.x * 31 + min((int)blockIdx.x, NHEAVY);

    uint32_t ea[4], eb[4];
    uint4 wv4;
    const uint32_t row_off = (cb + (tid >> 7) * BPW) * E_BYTES + (24 * (tw >> 5) + g) * 32 + t * 4;
#define LOAD_FIRST() do { \
        const uint32_t* pa = (const uint32_t*)((const uint8_t*)e + row_off); \
        const uint32_t* pc = pa + (96 + (g & 3) - 24 * (tw >> 5) - g) * 8; \
        ea[0] = ldg32(pa); ea[1] = ldg32(pa + 64); ea[2] = ldg32(pa + 4); ea[3] = ldg32(pa + 68); \
        eb[0] = ldg32(pa + 128); eb[1] = ldg32(pc); eb[2] = ldg32(pa + 132); eb[3] = ldg32(pc + 4); } while (0)
    if (tid < 128) {
        wv4 = __ldg((const uint4*)(wp.p[tid >> 5] + (tid < 96 ? lane * 8 : (lane & 15) * 16 + (lane >> 4) * 8)));
        LOAD_FIRST();
    }
    const int wid = uni(tid >> 5);
    const int wg = wid >> 2, w = wid & 3;
    const int b0 = cb + wg * BPW;
    const bool heavy = blockIdx.x < NHEAVY, helper = !heavy && wg == NWG - 1;
    const int fi = (blockIdx.x - NHEAVY) & 63, fb = (fi >> 2) * 8 + 4 + (fi & 3);
    const uint32_t wb = sb + wg * WG_SZ, bar0 = sb + SM_BAR + wg * (8 * BPW);

    if (lane == 0) {
        asm volatile("mbarrier.init.shared::cta.b64 [%0], 1;" :: "r"(bar0 + 16 * w) : "memory");
        asm volatile("mbarrier.init.shared::cta.b64 [%0], 1;" :: "r"(bar0 + 16 * w + 8) : "memory");
        if (w == 3) asm volatile("mbarrier.arrive.shared::cta.b64 _, [%0];" :: "r"(bar0 + 8 * (BPW - 1)) : "memory");
    }
    if (tw < 112) {
        const uint32_t one = tw < NF ? 0x3F80u : 0u;
        const bool mu = (MU_MASK >> (tw >> 3)) & 1;
        const uint32_t bh = one | (mu ? 0u : __float_as_uint(24192.f * 0x1p-79f));
        const uint32_t bl = one | (mu ? 0u : __float_as_uint(53.5f * 0x1p-79f));
        uint8_t* kvp = smem + wg * WG_SZ + WG_KV + tw * 16;
#pragma unroll
        for (int i = 0; i < 4; i++) {
            *(uint4*)(kvp + i * KV_SZ + KV_ONE) = make_uint4(bh, bl, bl, bh);
            if (tw >= NF) {
                *(uint4*)(kvp + i * KV_SZ + KV_V0) = make_uint4(0, 0, 0, 0);
                *(uint4*)(kvp + i * KV_SZ + KV_V1) = make_uint4(0, 0, 0, 0);
            }
        }
    }
    if (wg != 0) {
        if (wg == NWG - 1) bar_arrive(1, 256);
        asm volatile("fence.proxy.async.shared::cta;" ::: "memory");
        LOAD_FIRST();
    }
    const int mi = lane >> 3, mr = lane & 7;
    const uint32_t ea_off = opaque(wb + WG_KV + KV_E + (24 * w + (mi & 1) * 8 + mr) * 32 + (mi >> 1) * 16);
    const uint32_t eb_off = opaque(wb + WG_KV + KV_E + ((mi & 1) ? 96 + (mr & 3) : 24 * w + 16 + mr) * 32 + (mi >> 1) * 16);
    const uint32_t st1 = opaque(wb + WG_KV + ((mi & 2) ? KV_V0 : KV_K0) + (mi & 1) * L + (24 * w + mr) * 16);
    const uint32_t st3 = opaque((lane & 20) == 20 ? sb + SM_DUMMY : st1 + w * (KV_SZ - 24 * 16) + 96 * 16);
    const uint32_t ki1 = opaque(wb + WG_KI + (t >> 1) * L + (24 * w + g) * 16 + (t & 1) * 8);
    const uint32_t ki3d = uni((96 - 24 * w) * 16);
    const uint64_t dw1 = mkdesc(sb + SM_W + 512, 128, 256), dw2 = mkdesc(sb + SM_W, 128, 256);
    const uint32_t dki_lo = uni(((wb + WG_KI) >> 4) | ((L / 16) << 16));
    const uint32_t dkv_lo = uni((wb + WG_KV + KV_ONE) >> 4);
    const uint32_t auxa = opaque(t < 2 ? 0x1C800000u : 0u);
    const uint32_t kc = opaque(0x1F801F80u);
    const uint32_t ksc = uni(((MUW >> (tw >> 5)) & 1) ? 0x63006300u : 0x1C001C00u);
    const uint32_t wbar = __shfl_xor_sync(0xffffffffu, 1 + (tid >> 7), 1);
    const uint32_t tok_nx = __shfl_xor_sync(0xffffffffu, 1 + (((tid >> 7) + 1) & 3), 1);
    uint32_t chk = 0;
    uint32_t ql = 0, rl = 0;
    uint8_t* o1 = (uint8_t*)out + row_off;
    uint32_t bar = bar0;

    if (wg == 0) {
        uint32_t v[4] = {wv4.x, wv4.y, wv4.z, wv4.w}, u[4];
        const float c = 0.35355339059327373f * 1.4426950408889634f;
        const float sc = w == 0 ? 0x1p-71f : c * 0x1p-71f;
#pragma unroll
        for (int i = 0; i < 4; i++)
            u[i] = packbf(__float_as_uint(__uint_as_float(v[i] << 16) * sc), __float_as_uint(__uint_as_float(v[i] & 0xFFFF0000u) * sc));
        if (w != 1) *(uint4*)(smem + SM_W + tw * 16) = wv4;
        if (w < 2) *(uint4*)(smem + SM_W + (w == 0 ? 2048 : 0) + tw * 16) = make_uint4(u[0], u[1], u[2], u[3]);
        asm volatile("fence.proxy.async.shared::cta;" ::: "memory");
    }
    __syncthreads();
    if (wg == NWG - 1) {
        if (lane == 0) {
            const uint8_t* src = (const uint8_t*)e + (size_t)(cb + w * BPW + 1) * E_BYTES;
            const uint32_t dst = sb + w * WG_SZ + WG_KV + KV_E, br = sb + SM_BAR + w * (8 * BPW);
            load_e(dst, src, br);
            const long long c0 = clock64();
            while (clock64() - c0 < PFDELAY) {}
#pragma unroll 1
            for (int j = 1; j < 4; j++) load_e(dst + j * KV_SZ, src + j * E_BYTES, br + 8 * j);
        }
        __syncwarp();
    }

#pragma unroll 1
    for (int grp = 0; grp < BPW / 4; grp++) {
      uint32_t kvo = 0, dlo = dkv_lo;
      const int stop = uni((helper && grp) ? 3 : 4);
#pragma unroll 1
      for (int slot = 0; slot < 4; slot++) {
        uint32_t q0[2], q1[2], q2[2], r0[2], r1[2], r2[2];
        {
            bar_sync(wbar, 256);
            uint32_t d1[32], d2[32];
            WG_FENCE();
            wg_proj64(d1, ea[0], ea[1], ea[2], ea[3], dw1);
            wg_proj64(d2, eb[0], eb[1], eb[2], eb[3], dw2);
            WG_COMMIT();
            WG_WAIT0();
            TOK_PUT(1);
            pin<32>(d1); pin<32>(d2);
#pragma unroll
            for (int j = 0; j < 2; j++) {
                const uint32_t k0 = packbf(d1[24 + 2 * j], d1[25 + 2 * j]), k1 = packbf(d1[28 + 2 * j], d1[29 + 2 * j]);
                stsm4(st1 + kvo + 128 * j, k0, k1, packbf(d1[8 + 2 * j], d1[9 + 2 * j]), packbf(d1[12 + 2 * j], d1[13 + 2 * j]));
                sts64(ki1 + 128 * j, k0, k1);
            }
            {
                const uint32_t k0 = mulbf(packbf(d2[0], d2[1]), ksc), k1 = mulbf(packbf(d2[4], d2[5]), ksc);
                stsm4(st1 + kvo + 256, k0, k1, packbf(d2[16], d2[17]), packbf(d2[20], d2[21]));
                sts64(ki1 + 256, k0, k1);
            }
            q0[0] = packbf(d1[0], d1[1]); q0[1] = packbf(d1[2], d1[3]);
            q1[0] = packbf(d1[4], d1[5]); q1[1] = packbf(d1[6], d1[7]);
            q2[0] = packbf(d2[8], d2[9]); q2[1] = packbf(d2[12], d2[13]);
            r0[0] = packbf(d1[16], d1[17]); r0[1] = packbf(d1[18], d1[19]);
            r1[0] = packbf(d1[20], d1[21]); r1[1] = packbf(d1[22], d1[23]);
            r2[0] = packbf(d2[24], d2[25]); r2[1] = packbf(d2[28], d2[29]);
            pin<2>(q0); pin<2>(q1); pin<2>(q2); pin<2>(r0); pin<2>(r1); pin<2>(r2);
            if (w == slot) {
                const uint32_t k0 = mulbf(packbf(d2[2], d2[3]), 0x63006300u), k1 = mulbf(packbf(d2[6], d2[7]), 0x63006300u);
                stsm4(st3, k0, k1, packbf(d2[18], d2[19]), packbf(d2[22], d2[23]));
                sts64(ki1 + ki3d, k0, k1);
                ql = g < 4 ? packbf(d2[10], d2[11]) : packbf(d2[14], d2[15]);
                rl = g < 4 ? packbf(d2[26], d2[27]) : packbf(d2[30], d2[31]);
            }
        }
        TOK_PUT(5);
        asm volatile("fence.proxy.async.shared::cta;" ::: "memory");
        TOK_PUT(6);
        bar_sync(wbar, 128);
        TOK_PUT(7);
        if (slot == stop) {
            ea[0] = q0[0] ^ q0[1] ^ q1[0] ^ q1[1] ^ q2[0] ^ q2[1] ^ r0[0] ^ r0[1] ^ r1[0] ^ r1[1] ^ r2[0] ^ r2[1];
            TOK_PUT(2);
            break;
        }

        const uint64_t dk0 = mk64(dlo + ((KV_K0 / 16) << 16), 8);
        const uint64_t dv0 = mk64(dlo + (8 << 16), L / 16);
        const uint64_t dv1 = mk64(dlo + (8 << 16), 2 * L / 16);
        uint32_t s[52], p[26], o[12];
        WG_FENCE();
        wg_s104(s, auxa, auxa, q0[0], q0[1], dk0);
        WG_COMMIT(); TOK_PUT(2);
        WG_WAIT0(); pin<52>(s);
        exp_tile(p, s, kc, m1);
        WG_FENCE();
        pv_chain<8, false>(o, p, dv0, 0, 0);
        wg_s104(s, auxa, auxa, q1[0], q1[1], dk0 + ((L / 16) << 16));
        WG_COMMIT();
        WG_WAIT0(); pin<52>(s); pin<8>(o);
        finish((uint32_t*)o1, (uint32_t*)(o1 + 256), o[0], o[2], o[4], o[5], o[6], o[7], r0[0], r0[1], chk);
        exp_tile(p, s, kc, m1);
        WG_FENCE();
        pv_chain<8, false>(o, p, dv1, 0, 0);
        wg_s104sp(s, q2[0], q2[1], auxa, auxa, mk64(dki_lo, 8), 0xEEEE4444u);
        WG_COMMIT();
        WG_WAIT0(); pin<52>(s); pin<8>(o);
        finish((uint32_t*)(o1 + 16), (uint32_t*)(o1 + 272), o[0], o[2], o[4], o[5], o[6], o[7], r1[0], r1[1], chk);
        exp_tile(p, s, kc, m1);
        WG_FENCE();
        pv_chain<12, true>(o, p, dv0, 0, 0);
        WG_COMMIT();
        wait_bar(bar);
        ldsm4(ea, ea_off + kvo);
        ldsm4(eb, eb_off + kvo);
        WG_WAIT0(); pin<12>(o);
        finish((uint32_t*)(o1 + 512), (uint32_t*)(o1 + 528), o[0], o[2], o[4], o[5], o[10], o[11], r2[0], r2[1], chk);
        o1 += E_BYTES; bar += 8;
        kvo += KV_SZ; dlo += KV_SZ / 16;
      }
      if (grp == 0 && w < 3 && lane == 0)
          load_e(wb + WG_KV + KV_E + w * KV_SZ, (const uint8_t*)e + (size_t)((helper && w == 2) ? fb : b0 + 5 + w) * E_BYTES, bar0 + 8 * (4 + w));
      __syncwarp();
      if (!(heavy && grp)) {
            const uint32_t qa = g < 4 ? ql : 0, qb = g < 4 ? 0 : ql;
            const uint32_t qc = mulbf(mulbf(qa, 0x63006300u), 0x63006300u), qd = mulbf(mulbf(qb, 0x63006300u), 0x63006300u);
            uint32_t pl[13];
            const uint32_t ka = wb + WG_KV + w * KV_SZ + (mi & 1) * L + ((mi >> 1) * 8 + mr) * 16;
#pragma unroll
            for (int j = 0; j < 7; j++) {
                uint32_t kf[4], d[4];
                if (j < 6) ldsm4(kf, ka + KV_K0 + j * 256); else ldsm2(kf, ka + KV_K0 + j * 256);
                hmma0(d, qc, qa, qd, qb, kf[0], kf[1]);
                pl[2 * j] = !mufu_tile(2 * j) ? exp_mufu(d[0], d[1]) : exp_mufu(d[2], d[3]);
                if (j < 6) {
                    hmma0(d, qc, qa, qd, qb, kf[2], kf[3]);
                    pl[2 * j + 1] = !mufu_tile(2 * j + 1) ? exp_mufu(d[0], d[1]) : exp_mufu(d[2], d[3]);
                }
            }
            uint32_t ot[4], ls[4];
#pragma unroll
            for (int j = 0; j < 7; j++) {
                uint32_t vf[4];
                if (j < 6) ldsm4t(vf, ka + KV_V0 + j * 256); else ldsm2t(vf, ka + KV_V0 + j * 256);
                if (j == 0) hmma0(ot, vf[0], vf[1], vf[2], vf[3], pl[0], pl[1]);
                else if (j < 6) hmma(ot, vf[0], vf[1], vf[2], vf[3], pl[2 * j], pl[2 * j + 1]);
                else hmma8(ot, vf[0], vf[1], pl[12]);
            }
            hmma0(ls, pl[0], pl[1], pl[2], pl[3], 0x3F803F80u, 0x3F803F80u);
            hmma(ls, pl[4], pl[5], pl[6], pl[7], 0x3F803F80u, 0x3F803F80u);
            hmma(ls, pl[8], pl[9], pl[10], pl[11], 0x3F803F80u, 0x3F803F80u);
            hmma8(ls, pl[12], 0, t < 2 ? 0x3F803F80u : 0u);
            uint32_t l = __float_as_uint(__uint_as_float(ls[0]) + __uint_as_float(ls[2]));
            uint32_t r = __float_as_uint(rcp(l));
            const uint32_t rr = packbf(r, r);
            chk = __viaddmax_u16x2(rr, CHK_OFF, chk);
            uint32_t u = packbf(t < 2 ? ot[0] : ot[2], t < 2 ? ot[1] : ot[3]), y;
            asm volatile("movmatrix.sync.aligned.m8n8.trans.b16 %0, %0;" : "+r"(u));
            asm("fma.rn.relu.bf16x2 %0, %1, %2, %3;" : "=r"(y) : "r"(u), "r"(rr), "r"(rl));
            const int lb = w == stop ? fb : b0 + 4 * grp + w;
            *(uint32_t*)((uint8_t*)out + (size_t)lb * E_BYTES + (96 + (g & 3)) * 32 + (g >> 2) * 16 + t * 4) = y;
            if (grp == 0) bar_sync(wbar + 4, 128);
      }
    }
    if (wg == 0) bar_sync(wbar, 256);
    if (__syncthreads_or((chk & 0xFFFFu) > CHK_LIM || (chk >> 16) > CHK_LIM)) {
        for (int ib = 0; ib < NWG * BPW; ib++) {
            const size_t off = (size_t)((!heavy && ib == NWG * BPW - 1) ? fb : cb + ib) * NF * 16;
            slow_batch(e + off, wp.p[1], wp.p[0], wp.p[2], wp.p[3], out + off, (float*)smem, (float*)smem + NF * 16);
        }
    }
}

}

extern "C" void kernel_launch(void* const* d_in, const int* in_sizes, int n_in, void* d_out, int out_size) {
    cudaFuncSetAttribute(autoint_kernel, cudaFuncAttributeMaxDynamicSharedMemorySize, SM_TOTAL);
    Wp wp;
    wp.p[0] = (const __nv_bfloat16*)d_in[2]; wp.p[1] = (const __nv_bfloat16*)d_in[1];
    wp.p[2] = (const __nv_bfloat16*)d_in[3]; wp.p[3] = (const __nv_bfloat16*)d_in[4];
    autoint_kernel<<<NCTA, NWG * 128, SM_TOTAL>>>((const __nv_bfloat16*)d_in[0], wp, (__nv_bfloat16*)d_out, 0xFFFFFFFFu);
}
```
